```python
import torch

def _softmax(x, axis=-1):
    return torch.softmax(x, dim=axis)

def _gelu(x):
    return torch.nn.functional.gelu(x, approximate='tanh')

def _silu(x):
    return torch.nn.functional.silu(x)

def _sigmoid(x):
    return torch.sigmoid(x)

def _layernorm(x, axis=-1, eps=1e-05):
    m = x.mean(dim=axis, keepdim=True)
    v = x.var(dim=axis, keepdim=True, unbiased=False)
    return (x - m) / torch.sqrt(v + eps)

def _scatter_add(tgt, idx, src, axis=0):
    return tgt.clone().index_add_(axis, idx, src)

def _segment_sum(src, seg, n):
    out = torch.zeros((n,) + src.shape[1:], dtype=src.dtype)
    return out.index_add_(0, seg, src)

def _pad(x, pw):
    flat = tuple((v for pair in reversed(pw) for v in pair))
    return torch.nn.functional.pad(x, flat)
kernel_name = 'concat_heads__memory_aug_recurrent_mem_tr__memory_aug_recurrent_mem_tr__prompt'

def setup_inputs():

    _w = lambda a: (lambda t: t.to(torch.bfloat16) if t.is_floating_point() else t)(torch.as_tensor(a))

    def _A_setup():
        B, S, Dm = (1, 2048, 1024)
        H, Dh = (32, 128)
        M, seg = (8, 32)
        seg = min(seg, S)
        S = S // seg * seg
        return {'x': _w((lambda *s: torch.randn(*s, dtype=torch.bfloat16) * 0.05)(B, S, Dm)), 'mem0': _w((lambda *s: torch.randn(*s, dtype=torch.bfloat16) * 0.4)(B, M, Dm)), 'Wq': _w((lambda *s: torch.randn(*s, dtype=torch.bfloat16) * 6.4)(Dm, H, Dh) * Dm ** (-0.5)), 'Wk': _w((lambda *s: torch.randn(*s, dtype=torch.bfloat16) * 6.4)(Dm, H, Dh) * Dm ** (-0.5)), 'Wv': _w((lambda *s: torch.randn(*s, dtype=torch.bfloat16) * 0.4)(Dm, H, Dh) * Dm ** (-0.5)), 'Wo': _w((lambda *s: torch.randn(*s, dtype=torch.bfloat16) * 0.4)(H, Dh, Dm) * (H * Dh) ** (-0.5)), 'seg_len': seg}
    _A_in = _A_setup()

    def _B_setup():
        B, S, Dm = (1, 2048, 1024)
        H, Dh = (32, 128)
        M, seg = (8, 32)
        seg = min(seg, S)
        S = S // seg * seg
        return {'x': _w((lambda *s: torch.randn(*s, dtype=torch.bfloat16) * 0.05)(B, S, Dm)), 'mem0': _w((lambda *s: torch.randn(*s, dtype=torch.bfloat16) * 0.4)(B, M, Dm)), 'Wq': _w((lambda *s: torch.randn(*s, dtype=torch.bfloat16) * 6.4)(Dm, H, Dh) * Dm ** (-0.5)), 'Wk': _w((lambda *s: torch.randn(*s, dtype=torch.bfloat16) * 6.4)(Dm, H, Dh) * Dm ** (-0.5)), 'Wv': _w((lambda *s: torch.randn(*s, dtype=torch.bfloat16) * 0.4)(Dm, H, Dh) * Dm ** (-0.5)), 'Wo': _w((lambda *s: torch.randn(*s, dtype=torch.bfloat16) * 0.4)(H, Dh, Dm) * (H * Dh) ** (-0.5)), 'seg_len': seg}
    _B_in = _B_setup()
    return {'A_x': _A_in['x'], 'A_mem0': _A_in['mem0'], 'A_Wq': _A_in['Wq'], 'A_Wk': _A_in['Wk'], 'A_Wv': _A_in['Wv'], 'A_Wo': _A_in['Wo'], 'A_seg_len': _A_in['seg_len'], 'B_x': _B_in['x'], 'B_mem0': _B_in['mem0'], 'B_Wq': _B_in['Wq'], 'B_Wk': _B_in['Wk'], 'B_Wv': _B_in['Wv'], 'B_Wo': _B_in['Wo'], 'B_seg_len': _B_in['seg_len']}

def reference(A_x, A_mem0, A_Wq, A_Wk, A_Wv, A_Wo, A_seg_len, B_x, B_mem0, B_Wq, B_Wk, B_Wv, B_Wo, B_seg_len):

    def _A_ref(x, mem0, Wq, Wk, Wv, Wo, seg_len):
        B, S, Dm = x.shape
        H, Dh = (Wq.shape[1], Wq.shape[2])
        M = mem0.shape[1]
        scale = Dh ** (-0.5)
        n_seg = S // seg_len
        L = M + seg_len
        idx = torch.arange(L)
        mask = (idx[:, None] < M) | (idx[:, None] >= idx[None, :])
        mem = mem0
        outs = []
        for s in range(n_seg):
            xs = x[:, s * seg_len:(s + 1) * seg_len, :].clone()
            h = torch.concatenate([mem, xs], axis=1)
            q = torch.einsum('btd,dhe->bhte', h, Wq)
            k = torch.einsum('btd,dhe->bhte', h, Wk)
            v = torch.einsum('btd,dhe->bhte', h, Wv)
            scores = torch.einsum('bhqe,bhke->bhqk', q, k) * scale
            scores = torch.where(mask[None, None], scores, -1000000000.0)
            p = _softmax(scores, axis=-1)
            o = torch.einsum('bhqk,bhke->bhqe', p, v)
            o = torch.einsum('bhte,hed->btd', o, Wo)
            mem = o[:, :M, :].clone()
            outs.append(o[:, M:, :])
        return torch.concatenate(outs, axis=1)

    def _B_ref(x, mem0, Wq, Wk, Wv, Wo, seg_len):
        B, S, Dm = x.shape
        H, Dh = (Wq.shape[1], Wq.shape[2])
        M = mem0.shape[1]
        scale = Dh ** (-0.5)
        n_seg = S // seg_len
        L = M + seg_len
        idx = torch.arange(L)
        mask = (idx[:, None] < M) | (idx[:, None] >= idx[None, :])
        mem = mem0
        outs = []
        for s in range(n_seg):
            xs = x[:, s * seg_len:(s + 1) * seg_len, :].clone()
            h = torch.concatenate([mem, xs], axis=1)
            q = torch.einsum('btd,dhe->bhte', h, Wq)
            k = torch.einsum('btd,dhe->bhte', h, Wk)
            v = torch.einsum('btd,dhe->bhte', h, Wv)
            scores = torch.einsum('bhqe,bhke->bhqk', q, k) * scale
            scores = torch.where(mask[None, None], scores, -1000000000.0)
            p = _softmax(scores, axis=-1)
            o = torch.einsum('bhqk,bhke->bhqe', p, v)
            o = torch.einsum('bhte,hed->btd', o, Wo)
            mem = o[:, :M, :].clone()
            outs.append(o[:, M:, :])
        return torch.concatenate(outs, axis=1)
    a = _A_ref(A_x, A_mem0, A_Wq, A_Wk, A_Wv, A_Wo, A_seg_len)
    b = _B_ref(B_x, B_mem0, B_Wq, B_Wk, B_Wv, B_Wo, B_seg_len)
    return torch.concatenate([a, b], axis=-1)
```

```cpp
#include <cuda_runtime.h>
#include <cuda_bf16.h>
#include <cuda.h>
#include <stdint.h>

typedef __nv_bfloat16 bf16;

constexpr int S_ = 2048, DM = 1024, NH = 32, DH = 128, HD = NH * DH  , MT = 8, SEG = 32, NSEG = 64;

__device__ __align__(1024) bf16 g_qkv[(size_t)2 * 3 * S_ * HD];
__device__ __align__(1024) bf16 g_kvm[(size_t)2 * NSEG * 2 * MT * HD];
__device__ __align__(1024) bf16 g_o[(size_t)2 * S_ * HD];
constexpr int RING = 4;
constexpr int MB_BLK = 65536, MB_SLOT = 16384;
__device__ __align__(65536) unsigned char g_mb[132 * MB_BLK];
struct Ctrl {
  unsigned head[3][32];
  unsigned kv_ready[2 * NSEG];
  unsigned o_ready[2 * 32];
  unsigned quart[64 * 4];
  unsigned split[32];
  unsigned place[128];
  unsigned q_ready[16];
  unsigned kvx_ready[16];
};
__device__ Ctrl g_ctrl;

__device__ __forceinline__ uint32_t smem_u32(const void* p) { return (uint32_t)__cvta_generic_to_shared(p); }
__device__ __forceinline__ void mbar_init(uint32_t a, uint32_t c) { asm volatile("mbarrier.init.shared::cta.b64 [%0], %1;" ::"r"(a), "r"(c) : "memory"); }
__device__ __forceinline__ void mbar_expect(uint32_t a, uint32_t b) { asm volatile("mbarrier.arrive.expect_tx.shared::cta.b64 _, [%0], %1;" ::"r"(a), "r"(b) : "memory"); }
__device__ __forceinline__ void mbar_arrive(uint32_t a) { asm volatile("mbarrier.arrive.shared::cta.b64 _, [%0];" ::"r"(a) : "memory"); }
__device__ __forceinline__ void mbar_wait(uint32_t a, uint32_t ph) {
  asm volatile(
      "{\n.reg .pred p;\n.reg .u32 n;\n"
      "mbarrier.try_wait.parity.shared::cta.b64 p, [%0], %1;\n"
      "@p bra DONE;\n"
      "mov.u32 n, 0;\n"
      "LOOP:\n"
      "mbarrier.try_wait.parity.shared::cta.b64 p, [%0], %1;\n"
      "@p bra DONE;\n"
      "add.u32 n, n, 1;\n"
      "setp.lt.u32 p, n, 0x1000000;\n"
      "@p bra LOOP;\n"
      "trap;\n"
      "DONE:\n}\n" ::"r"(a), "r"(ph) : "memory");
}
__device__ __forceinline__ void mbar_wait_u(uint32_t a, uint32_t ph) {
  asm volatile(
      "{\n.reg .pred p;\n.reg .u32 n;\n"
      "mbarrier.try_wait.parity.shared::cta.b64 p, [%0], %1;\n"
      "@p bra.uni DONE;\n"
      "mov.u32 n, 0;\n"
      "LOOP:\n"
      "mbarrier.try_wait.parity.shared::cta.b64 p, [%0], %1;\n"
      "@p bra.uni DONE;\n"
      "add.u32 n, n, 1;\n"
      "setp.lt.u32 p, n, 0x1000000;\n"
      "@p bra.uni LOOP;\n"
      "trap;\n"
      "DONE:\n}\n" ::"r"(a), "r"(ph) : "memory");
}
__device__ __forceinline__ bool mbar_test(uint32_t a, uint32_t ph) {
  uint32_t ok;
  asm volatile("{.reg .pred p; mbarrier.test_wait.parity.shared::cta.b64 p, [%1], %2; selp.u32 %0, 1, 0, p;}"
               : "=r"(ok) : "r"(a), "r"(ph) : "memory");
  return __all_sync(~0u, ok);
}
__device__ __forceinline__ void tma_load_2d(uint32_t dst, const CUtensorMap* m, int c0, int c1, uint32_t bar) {
  asm volatile("cp.async.bulk.tensor.2d.shared::cluster.global.mbarrier::complete_tx::bytes [%0], [%1, {%3, %4}], [%2];"
               ::"r"(dst), "l"(m), "r"(bar), "r"(c0), "r"(c1) : "memory");
}
__device__ __forceinline__ void tma_store_2d(const CUtensorMap* m, uint32_t src, int c0, int c1) {
  asm volatile("cp.async.bulk.tensor.2d.global.shared::cta.bulk_group [%0, {%2, %3}], [%1];"
               ::"l"(m), "r"(src), "r"(c0), "r"(c1) : "memory");
}
__device__ __forceinline__ uint64_t policy_evict_first() {
  uint64_t p;
  asm volatile("createpolicy.fractional.L2::evict_first.b64 %0, 1.0;" : "=l"(p));
  return p;
}
__device__ __forceinline__ void tma_load_2d_h(uint32_t dst, const CUtensorMap* m, int c0, int c1, uint32_t bar, uint64_t pol) {
  asm volatile("cp.async.bulk.tensor.2d.shared::cluster.global.mbarrier::complete_tx::bytes.L2::cache_hint [%0], [%1, {%3, %4}], [%2], %5;"
               ::"r"(dst), "l"(m), "r"(bar), "r"(c0), "r"(c1), "l"(pol) : "memory");
}
__device__ __forceinline__ void tma_load_4d_h(uint32_t dst, const CUtensorMap* m, int c1, int c2, int c3, uint32_t bar, uint64_t pol) {
  asm volatile("cp.async.bulk.tensor.4d.shared::cluster.global.mbarrier::complete_tx::bytes.L2::cache_hint [%0], [%1, {%3, %4, %5, %6}], [%2], %7;"
               ::"r"(dst), "l"(m), "r"(bar), "r"(0), "r"(c1), "r"(c2), "r"(c3), "l"(pol) : "memory");
}
__device__ __forceinline__ void tma_store_2d_h(const CUtensorMap* m, uint32_t src, int c0, int c1, uint64_t pol) {
  asm volatile("cp.async.bulk.tensor.2d.global.shared::cta.bulk_group.L2::cache_hint [%0, {%2, %3}], [%1], %4;"
               ::"l"(m), "r"(src), "r"(c0), "r"(c1), "l"(pol) : "memory");
}
__device__ __forceinline__ void fence_async() { asm volatile("fence.proxy.async.shared::cta;" ::: "memory"); }
__device__ __forceinline__ void named_bar(int id, int n) { asm volatile("bar.sync %0, %1;" ::"r"(id), "r"(n) : "memory"); }
__device__ __forceinline__ uint32_t mapa(uint32_t a, uint32_t r) {
  uint32_t o;
  asm("mapa.shared::cluster.u32 %0, %1, %2;" : "=r"(o) : "r"(a), "r"(r));
  return o;
}
__device__ __forceinline__ void cluster_sync() {
  asm volatile("barrier.cluster.arrive.release.aligned; barrier.cluster.wait.acquire.aligned;" ::: "memory");
}
__device__ __forceinline__ uint32_t pack_bf16(float lo, float hi) {
  uint32_t r;
  asm("cvt.rn.bf16x2.f32 %0, %1, %2;" : "=r"(r) : "f"(hi), "f"(lo));
  return r;
}
__device__ __forceinline__ void mma16816(float* d, uint32_t a0, uint32_t a1, uint32_t a2, uint32_t a3, uint32_t b0, uint32_t b1) {
  asm("mma.sync.aligned.m16n8k16.row.col.f32.bf16.bf16.f32 {%0,%1,%2,%3}, {%4,%5,%6,%7}, {%8,%9}, {%0,%1,%2,%3};"
      : "+f"(d[0]), "+f"(d[1]), "+f"(d[2]), "+f"(d[3]) : "r"(a0), "r"(a1), "r"(a2), "r"(a3), "r"(b0), "r"(b1));
}
__device__ __forceinline__ void mma1688(float* d, uint32_t a0, uint32_t a1, uint32_t b0) {
  asm("mma.sync.aligned.m16n8k8.row.col.f32.bf16.bf16.f32 {%0,%1,%2,%3}, {%4,%5}, {%6}, {%0,%1,%2,%3};"
      : "+f"(d[0]), "+f"(d[1]), "+f"(d[2]), "+f"(d[3]) : "r"(a0), "r"(a1), "r"(b0));
}
__device__ __forceinline__ void ldsm_x4(uint32_t* r, uint32_t a) {
  asm volatile("ldmatrix.sync.aligned.m8n8.x4.shared.b16 {%0,%1,%2,%3}, [%4];" : "=r"(r[0]), "=r"(r[1]), "=r"(r[2]), "=r"(r[3]) : "r"(a) : "memory");
}
__device__ __forceinline__ void ldsm_x4_if(uint32_t* r, uint32_t a, uint32_t pred) {
  asm volatile("{.reg .pred p; setp.ne.u32 p, %5, 0;\n@p ldmatrix.sync.aligned.m8n8.x4.shared.b16 {%0,%1,%2,%3}, [%4];}"
               : "+r"(r[0]), "+r"(r[1]), "+r"(r[2]), "+r"(r[3]) : "r"(a), "r"(pred) : "memory");
}
__device__ __forceinline__ void ldsm_x4_t(uint32_t* r, uint32_t a) {
  asm volatile("ldmatrix.sync.aligned.m8n8.x4.trans.shared.b16 {%0,%1,%2,%3}, [%4];" : "=r"(r[0]), "=r"(r[1]), "=r"(r[2]), "=r"(r[3]) : "r"(a) : "memory");
}
__device__ __forceinline__ void ldsm_x2_t(uint32_t* r, uint32_t a) {
  asm volatile("ldmatrix.sync.aligned.m8n8.x2.trans.shared.b16 {%0,%1}, [%2];" : "=r"(r[0]), "=r"(r[1]) : "r"(a) : "memory");
}
__device__ __forceinline__ void stsm_x4(uint32_t a, uint32_t r0, uint32_t r1, uint32_t r2, uint32_t r3) {
  asm volatile("stmatrix.sync.aligned.m8n8.x4.shared.b16 [%0], {%1,%2,%3,%4};" ::"r"(a), "r"(r0), "r"(r1), "r"(r2), "r"(r3) : "memory");
}
__device__ __forceinline__ uint4 ld_relaxed4(const void* p) {
  uint4 v;
  asm volatile("ld.relaxed.gpu.global.v4.u32 {%0,%1,%2,%3}, [%4];" : "=r"(v.x), "=r"(v.y), "=r"(v.z), "=r"(v.w) : "l"(p) : "memory");
  return v;
}
__device__ __forceinline__ void st_relaxed2(void* p, uint32_t a, uint32_t b) {
  asm volatile("st.relaxed.gpu.global.v2.u32 [%0], {%1,%2};" ::"l"(p), "r"(a), "r"(b) : "memory");
}
__device__ __forceinline__ void st_relaxed1(void* p, uint32_t a) {
  asm volatile("st.relaxed.gpu.global.u32 [%0], %1;" ::"l"(p), "r"(a) : "memory");
}
__device__ __forceinline__ uint4 lds128(uint32_t a) {
  uint4 v;
  asm volatile("ld.shared.v4.u32 {%0,%1,%2,%3}, [%4];" : "=r"(v.x), "=r"(v.y), "=r"(v.z), "=r"(v.w) : "r"(a));
  return v;
}
__device__ __forceinline__ void sts128(uint32_t a, uint32_t x, uint32_t y, uint32_t z, uint32_t w) {
  asm volatile("st.shared.v4.u32 [%0], {%1,%2,%3,%4};" ::"r"(a), "r"(x), "r"(y), "r"(z), "r"(w) : "memory");
}
__device__ __forceinline__ void sts32(uint32_t a, uint32_t x) { asm volatile("st.shared.u32 [%0], %1;" ::"r"(a), "r"(x) : "memory"); }
__device__ __forceinline__ float ex2(float x) {
  float y;
  asm("ex2.approx.ftz.f32 %0, %1;" : "=f"(y) : "f"(x));
  return y;
}

constexpr int G_STAGES = 4;
constexpr int G_STAGE_BYTES = 16384 + 32768;
constexpr int G_EPI_BYTES = 2 * 16384;
constexpr int G_SMEM = G_STAGES * G_STAGE_BYTES + G_EPI_BYTES + 1024 + 128;

struct GemmMaps {
  CUtensorMap a[2];
  CUtensorMap b[6];
  CUtensorMap c;
};

__device__ __forceinline__ uint64_t mkdesc(uint32_t addr, uint32_t lbo, uint32_t sbo) {
  return (uint64_t)((addr & 0x3FFFF) >> 4) | ((uint64_t)(lbo >> 4) << 16) | ((uint64_t)(sbo >> 4) << 32) | (1ull << 62);
}

#define ACC8(i) "+f"(d[i]), "+f"(d[i + 1]), "+f"(d[i + 2]), "+f"(d[i + 3]), "+f"(d[i + 4]), "+f"(d[i + 5]), "+f"(d[i + 6]), "+f"(d[i + 7])
__device__ __forceinline__ void wgmma_n256(float* d, uint64_t da, uint64_t db, int scale_d) {
  asm volatile(
      "{.reg .pred p; setp.ne.b32 p, %130, 0;\n"
      "wgmma.mma_async.sync.aligned.m64n256k16.f32.bf16.bf16 "
      "{%0,%1,%2,%3,%4,%5,%6,%7,%8,%9,%10,%11,%12,%13,%14,%15,"
      "%16,%17,%18,%19,%20,%21,%22,%23,%24,%25,%26,%27,%28,%29,%30,%31,"
      "%32,%33,%34,%35,%36,%37,%38,%39,%40,%41,%42,%43,%44,%45,%46,%47,"
      "%48,%49,%50,%51,%52,%53,%54,%55,%56,%57,%58,%59,%60,%61,%62,%63,"
      "%64,%65,%66,%67,%68,%69,%70,%71,%72,%73,%74,%75,%76,%77,%78,%79,"
      "%80,%81,%82,%83,%84,%85,%86,%87,%88,%89,%90,%91,%92,%93,%94,%95,"
      "%96,%97,%98,%99,%100,%101,%102,%103,%104,%105,%106,%107,%108,%109,%110,%111,"
      "%112,%113,%114,%115,%116,%117,%118,%119,%120,%121,%122,%123,%124,%125,%126,%127},"
      " %128, %129, p, 1, 1, 0, 1;}\n"
      : ACC8(0), ACC8(8), ACC8(16), ACC8(24), ACC8(32), ACC8(40), ACC8(48), ACC8(56),
        ACC8(64), ACC8(72), ACC8(80), ACC8(88), ACC8(96), ACC8(104), ACC8(112), ACC8(120)
      : "l"(da), "l"(db), "r"(scale_d));
}

__device__ __forceinline__ void wgmma_n64(float* d, uint64_t da, uint64_t db) {
  asm volatile(
      "wgmma.mma_async.sync.aligned.m64n64k16.f32.bf16.bf16 "
      "{%0,%1,%2,%3,%4,%5,%6,%7,%8,%9,%10,%11,%12,%13,%14,%15,"
      "%16,%17,%18,%19,%20,%21,%22,%23,%24,%25,%26,%27,%28,%29,%30,%31},"
      " %32, %33, 1, 1, 1, 0, 1;\n"
      : ACC8(0), ACC8(8), ACC8(16), ACC8(24)
      : "l"(da), "l"(db));
}
#define K1_KV 24
#define K1_Q 0
#define FG 8
constexpr int K1_TILES = 768 + K1_KV + K1_Q;
__device__ __forceinline__ void gemm_tile_coords(int t, int& ai, int& arow, int& bi, int& bcol, int& crow, int& ccol) {
  int m, nb, w;
  if (t >= K1_KV + K1_Q) {
    t -= K1_KV + K1_Q;
    m = t & 15; nb = (t >> 4) & 15; w = t >> 8;
  } else if (t < K1_KV) {
    m = (t / (32 * FG)) * FG + t % FG; nb = (t / FG) & 31;
    w = 4 + (nb >> 4); nb &= 15;
  } else {
    t -= K1_KV;
    m = (t / (16 * FG)) * FG + t % FG; nb = (t / FG) & 15; w = 3;
  }
  ai = w >= 3; arow = m * 128; bi = w; bcol = nb * 256;
  crow = w * S_ + m * 128; ccol = bcol;
}
constexpr int N_FIL = 768 - K1_KV - K1_Q;
__host__ __device__ constexpr int fil_kv(int g) { return (g + 1) * 32 * FG <= K1_KV ? 0 : g * 32 * FG >= K1_KV ? 32 * FG : (g + 1) * 32 * FG - K1_KV; }
__host__ __device__ constexpr int fil_q(int g) { return (g + 1) * 16 * FG <= K1_Q ? 0 : g * 16 * FG >= K1_Q ? 16 * FG : (g + 1) * 16 * FG - K1_Q; }
__device__ __forceinline__ void filler_coords(int f, int& blk, int& w, int& nb) {
  int g = 0;
  while (g < 16 / FG - 1 && f >= fil_kv(g) + fil_q(g)) { f -= fil_kv(g) + fil_q(g); g++; }
  if (f < fil_kv(g)) { f += 32 * FG - fil_kv(g); w = 1 + f / (16 * FG); }
  else { f += 16 * FG - fil_q(g) - fil_kv(g); w = 0; }
  nb = (f / FG) & 15;
  blk = g * FG + f % FG;
}

__global__ void __launch_bounds__(384, 1) gemm_kernel(const __grid_constant__ GemmMaps maps) {
  constexpr int ntiles = K1_TILES, kblocks = 16;
  extern __shared__ unsigned char smem_raw[];
  uint32_t sb = (smem_u32(smem_raw) + 1023) & ~1023u;
  uint32_t epi = sb + G_STAGES * G_STAGE_BYTES;
  uint32_t bars = epi + G_EPI_BYTES;
  int wg = threadIdx.x >> 7;
  if (threadIdx.x == 0) {
    for (int i = 0; i < G_STAGES; i++) { mbar_init(bars + 8 * i, 1); mbar_init(bars + 32 + 8 * i, 2); }
    asm volatile("fence.mbarrier_init.release.cluster;" ::: "memory");
  }
  if (blockIdx.x == 0) {
    for (int i = threadIdx.x; i < (int)(sizeof(Ctrl) / 4); i += 384) ((unsigned*)&g_ctrl)[i] = 0;
    __threadfence();
  }
  __syncthreads();
  asm volatile("griddepcontrol.launch_dependents;");
  if (wg == 2) {
    asm volatile("setmaxnreg.dec.sync.aligned.u32 40;");
    if (threadIdx.x == 256) {
      int st = 0; uint32_t ph = 1;
      for (int t = blockIdx.x; t < ntiles; t += gridDim.x) {
        int ai, arow, bi, bcol, crow, ccol;
        gemm_tile_coords(t, ai, arow, bi, bcol, crow, ccol);
        for (int kb = 0; kb < kblocks; kb++) {
          mbar_wait(bars + 32 + 8 * st, ph);
          uint32_t fb = bars + 8 * st, sa = sb + st * G_STAGE_BYTES;
          mbar_expect(fb, G_STAGE_BYTES);
          tma_load_2d(sa, &maps.a[ai], kb * 64, arow, fb);
#pragma unroll
          for (int j = 0; j < 4; j++) tma_load_2d(sa + 16384 + j * 8192, &maps.b[bi], bcol + j * 64, kb * 64, fb);
          if (++st == G_STAGES) { st = 0; ph ^= 1; }
        }
      }
    }
  } else {
    asm volatile("setmaxnreg.inc.sync.aligned.u32 232;");
    int st = 0; uint32_t ph = 0;
    int tid = threadIdx.x & 127, warp = tid >> 5, lane = tid & 31;
    uint32_t myepi = epi + wg * 16384;
    float d[128];
    for (int t = blockIdx.x; t < ntiles; t += gridDim.x) {
      int ai, arow, bi, bcol, crow, ccol;
      gemm_tile_coords(t, ai, arow, bi, bcol, crow, ccol);
      int prev = -1;
      for (int kb = 0; kb < kblocks; kb++) {
        mbar_wait(bars + 8 * st, ph);
        uint32_t sa = sb + st * G_STAGE_BYTES;
        asm volatile("wgmma.fence.sync.aligned;" ::: "memory");
#pragma unroll
        for (int k = 0; k < 4; k++)
          wgmma_n256(d, mkdesc(sa + wg * 8192 + k * 32, 16, 1024), mkdesc(sa + 16384 + k * 2048, 8192, 1024), (kb | k) != 0);
        asm volatile("wgmma.commit_group.sync.aligned;" ::: "memory");
        asm volatile("wgmma.wait_group.sync.aligned 1;" ::: "memory");
        if (prev >= 0 && tid == 0) mbar_arrive(bars + 32 + 8 * prev);
        prev = st;
        if (++st == G_STAGES) { st = 0; ph ^= 1; }
      }
      asm volatile("wgmma.wait_group.sync.aligned 0;" ::: "memory");
      if (tid == 0) mbar_arrive(bars + 32 + 8 * prev);
#pragma unroll
      for (int hf = 0; hf < 2; hf++) {
        if (tid == 0) asm volatile("cp.async.bulk.wait_group.read 0;" ::: "memory");
        named_bar(1 + wg, 128);
        int row = warp * 16 + (lane & 7) + ((lane >> 3) & 1) * 8;
#pragma unroll
        for (int j = 0; j < 8; j++) {
          const float* s = d + hf * 64 + j * 8;
          int chunk = (j & 3) * 2 + (lane >> 4);
          uint32_t a = myepi + (j >> 2) * 8192 + row * 128 + ((chunk ^ (row & 7)) << 4);
          stsm_x4(a, pack_bf16(s[0], s[1]), pack_bf16(s[2], s[3]), pack_bf16(s[4], s[5]), pack_bf16(s[6], s[7]));
        }
        fence_async();
        named_bar(1 + wg, 128);
        if (tid == 0) {
          const uint64_t evf = policy_evict_first();
          tma_store_2d_h(&maps.c, myepi, ccol + hf * 128, crow + wg * 64, evf);
          tma_store_2d_h(&maps.c, myepi + 8192, ccol + hf * 128 + 64, crow + wg * 64, evf);
          asm volatile("cp.async.bulk.commit_group;" ::: "memory");
        }
      }
    }
    if (tid == 0) asm volatile("cp.async.bulk.wait_group 0;" ::: "memory");
  }
}

#define NSMALL 3
#define AR 4
#define ACLASS 6
#define ALAG 8
#define AFINE 4
constexpr int N_ATT1 = (2 * NSEG - AFINE) * (8 / AR), N_ATT = N_ATT1 + AFINE * 8;
__device__ __forceinline__ void att_coords(unsigned a, int& p, int& seg, int& h0, int& rounds) {
  int sg;
  if (a < N_ATT1) { sg = a / (8 / AR); h0 = (a % (8 / AR)) * 4 * AR; rounds = AR; }
  else { sg = 2 * NSEG - AFINE + ((a - N_ATT1) >> 3); h0 = ((a - N_ATT1) & 7) * 4; rounds = 1; }
  p = sg >> 6; seg = sg & 63;
}
constexpr int N_BIG = (32 - NSMALL) * 4;
#define KSPLIT 2
constexpr int N_SM1 = NSMALL * 32 - 16;
#define NQ 20
constexpr int N_FULL = N_BIG - NQ, N_MID = N_FULL + 4 * NQ;
constexpr int N_OUT = N_MID + N_SM1 + 16 * KSPLIT;
__device__ float4 g_park[(size_t)NQ * 2 * 3 * 4096 + 1];
__device__ float4 g_part[16 * (KSPLIT - 1) * 1024 + 1];
__device__ __forceinline__ void small_coords(int idx, int& tile, int& kb0, int& kb1) {
  if (idx < N_SM1) { tile = idx; kb0 = 0; kb1 = 32; }
  else { tile = N_SM1 + (idx - N_SM1) / KSPLIT; kb0 = ((idx - N_SM1) % KSPLIT) * (32 / KSPLIT); kb1 = kb0 + 32 / KSPLIT; }
}
constexpr int W_SMEM = G_SMEM + 192;
constexpr int A_SLOTS = 6, A_BYTES = 28672;

struct WorkerMaps {
  CUtensorMap qkv4;
  CUtensorMap kvm4;
  CUtensorMap o16;
  CUtensorMap o128;
  CUtensorMap o64;
  CUtensorMap wo[2];
  CUtensorMap out;
  CUtensorMap xb;
  CUtensorMap wb[3];
  CUtensorMap qkv64;
};

__device__ __forceinline__ unsigned ld_acquire(const unsigned* p) {
  unsigned v;
  asm volatile("ld.acquire.gpu.global.u32 %0, [%1];" : "=r"(v) : "l"(p) : "memory");
  return v;
}
__device__ __forceinline__ unsigned ld_relaxed1(const unsigned* p) {
  unsigned v;
  asm volatile("ld.relaxed.gpu.global.u32 %0, [%1];" : "=r"(v) : "l"(p) : "memory");
  return v;
}
__device__ __forceinline__ void red_release(unsigned* p) {
  asm volatile("red.release.gpu.global.add.u32 [%0], 1;" ::"l"(p) : "memory");
}

template <bool ACQ>
__device__ __forceinline__ bool att_ready(unsigned a) {
  int p, seg, h0, rounds;
  att_coords(a, p, seg, h0, rounds);
  const unsigned* pk = &g_ctrl.kv_ready[p * NSEG + seg];
  const unsigned* pq = &g_ctrl.q_ready[seg / (4 * FG)];
  unsigned k = ACQ ? ld_acquire(pk) : ld_relaxed1(pk), q = ACQ ? ld_acquire(pq) : ld_relaxed1(pq);
  return k >= 96 && (p == 0 || q >= 2 * fil_q(seg / (4 * FG)));
}
template <bool ACQ>
__device__ __forceinline__ bool out_ready(unsigned o) {
  const unsigned big = o < N_FULL ? o : N_FULL + ((o - N_FULL) >> 2);
  const unsigned* px = &g_ctrl.o_ready[o < N_MID ? (big >> 2) * 2 : (32 - NSMALL) * 2 + min((o - N_MID) >> 4, NSMALL * 2u - 1)];
  const unsigned* py = o < N_MID ? px + 1 : &g_ctrl.kv_ready[2 * NSEG - 1];
  unsigned x = ACQ ? ld_acquire(px) : ld_relaxed1(px), y = ACQ ? ld_acquire(py) : ld_relaxed1(py);
  return x >= 128 && y >= (o < N_MID ? 128 : 96);
}

__device__ __forceinline__ unsigned next_task(uint32_t tdone, uint32_t all_done, bool att_class) {
  Ctrl* C = &g_ctrl;
  for (unsigned spin = 0;; spin++) {
    unsigned a = ld_relaxed1(&C->head[0][0]), o = ld_relaxed1(&C->head[1][0]), f = ld_relaxed1(&C->head[2][0]);
    uint32_t done;
    asm volatile("ld.volatile.shared.u32 %0, [%1];" : "=r"(done) : "r"(tdone) : "memory");
    const bool idle = done == all_done;
    bool ra = a < N_ATT && att_ready<false>(a) && (a < N_ATT1 || idle);
    bool ro = o < N_OUT && out_ready<false>(o) && (o < N_MID || idle);
    if (a < N_ATT1) {
      if (att_class) { ro = false; f = N_FIL; }
      else if (ra && (ro || f < N_FIL)) ra = a + ALAG < N_ATT1 && att_ready<false>(a + ALAG);
    }
    if (ra) {
      a = atomicAdd(&C->head[0][0], 1);
      if (a < N_ATT) {
        for (unsigned n = 0; !att_ready<true>(a); n++) {
          __nanosleep(100);
          if (n > (1u << 22)) __trap();
        }
        return a;
      }
      continue;
    }
    if (ro && f >= N_FIL) {
      o = atomicAdd(&C->head[1][0], 1);
      if (o < N_OUT) {
        for (unsigned n = 0; !out_ready<true>(o); n++) {
          __nanosleep(100);
          if (n > (1u << 22)) __trap();
        }
        return o < N_FULL ? (1u << 16) | o : o < N_MID ? (1u << 16) | (N_FULL + ((o - N_FULL) >> 2)) | ((1 + ((o - N_FULL) & 3)) << 8) : (3u << 16) | (o - N_MID);
      }
      continue;
    }
    if (f < N_FIL) {
      f = atomicAdd(&C->head[2][0], 1);
      if (f < N_FIL) return (2u << 16) | f;
      continue;
    }
    if (a >= N_ATT && o >= N_OUT) return 0xFFFFFFFFu;
    __nanosleep(200 + (blockIdx.x & 7) * 60);
    if (spin > (1u << 22)) __trap();
  }
}

__device__ __forceinline__ void attn_unit(uint32_t ub, int hf, int lane, const CUtensorMap* omap, int orow, int ocol) {
  const uint32_t Qb = ub, Kb = ub + 8192, Vb = ub + 16384, Mb = ub + 24576;
  const int g = lane >> 2, c = lane & 3, l7 = lane & 7;
  float s[5][4];
#pragma unroll
  for (int i = 0; i < 5; i++) s[i][0] = s[i][1] = s[i][2] = s[i][3] = 0.f;
  const uint32_t qrow = Qb + (hf * 16 + l7 + ((lane >> 3) & 1) * 8) * 128;
#pragma unroll
  for (int ks = 0; ks < 8; ks += 2) {
    uint32_t a0[4], a1[4];
    const int hb = ks >> 2, c0 = (ks & 3) * 2;
    ldsm_x4(a0, qrow + hb * 4096 + (((c0 + (lane >> 4)) ^ l7) << 4));
    ldsm_x4(a1, qrow + hb * 4096 + (((c0 + 2 + (lane >> 4)) ^ l7) << 4));
#pragma unroll
    for (int nt = 0; nt < 5; nt++) {
      if (nt == 2 || nt == 3) { if (hf == 0) continue; }
      uint32_t b[4];
      ldsm_x4(b, (nt < 4 ? Kb + hb * 4096 + nt * 1024 : Mb + hb * 1024) + l7 * 128 + (((c0 + (lane >> 3)) ^ l7) << 4));
      mma16816(s[nt], a0[0], a0[1], a0[2], a0[3], b[0], b[1]);
      mma16816(s[nt], a1[0], a1[1], a1[2], a1[3], b[2], b[3]);
    }
  }
  const float sc = 0.08838834764831845f * 1.4426950408889634f;
  const int q0 = hf * 16 + g, q1 = q0 + 8;
  float m0 = -3.0e38f, m1 = -3.0e38f;
#pragma unroll
  for (int nt = 0; nt < 5; nt++) {
#pragma unroll
    for (int j = 0; j < 2; j++) {
      const int key = nt * 8 + 2 * c + j;
      if (nt < 4 && key > q0) s[nt][j] = -3.0e38f;
      if (nt < 4 && key > q1) s[nt][2 + j] = -3.0e38f;
      m0 = fmaxf(m0, s[nt][j]); m1 = fmaxf(m1, s[nt][2 + j]);
    }
  }
  m0 = fmaxf(m0, __shfl_xor_sync(~0u, m0, 1)); m0 = fmaxf(m0, __shfl_xor_sync(~0u, m0, 2));
  m1 = fmaxf(m1, __shfl_xor_sync(~0u, m1, 1)); m1 = fmaxf(m1, __shfl_xor_sync(~0u, m1, 2));
  float l0 = 0.f, l1 = 0.f;
#pragma unroll
  for (int nt = 0; nt < 5; nt++) {
#pragma unroll
    for (int j = 0; j < 2; j++) {
      const int key = nt * 8 + 2 * c + j;
      s[nt][j] = (nt < 4 && key > q0) ? 0.f : ex2((s[nt][j] - m0) * sc); l0 += s[nt][j];
      s[nt][2 + j] = (nt < 4 && key > q1) ? 0.f : ex2((s[nt][2 + j] - m1) * sc); l1 += s[nt][2 + j];
    }
  }
  l0 += __shfl_xor_sync(~0u, l0, 1); l0 += __shfl_xor_sync(~0u, l0, 2);
  l1 += __shfl_xor_sync(~0u, l1, 1); l1 += __shfl_xor_sync(~0u, l1, 2);
  const float i0 = 1.f / l0, i1 = 1.f / l1;
  uint32_t pa[5][2];
#pragma unroll
  for (int nt = 0; nt < 5; nt++) {
    pa[nt][0] = pack_bf16(s[nt][0] * i0, s[nt][1] * i0);
    pa[nt][1] = pack_bf16(s[nt][2] * i1, s[nt][3] * i1);
  }
  __syncwarp();
#pragma unroll
  for (int np = 0; np < 8; np++) {
    float o0[4] = {0.f, 0.f, 0.f, 0.f}, o1[4] = {0.f, 0.f, 0.f, 0.f};
    const uint32_t vb = Vb + (np >> 2) * 4096;
    const int c0 = (np & 3) * 2;
    {
      uint32_t b[4];
      ldsm_x4_t(b, vb + (l7 + ((lane >> 3) & 1) * 8) * 128 + (((c0 + (lane >> 4)) ^ l7) << 4));
      mma16816(o0, pa[0][0], pa[0][1], pa[1][0], pa[1][1], b[0], b[1]);
      mma16816(o1, pa[0][0], pa[0][1], pa[1][0], pa[1][1], b[2], b[3]);
    }
    if (hf) {
      uint32_t b[4];
      ldsm_x4_t(b, vb + (16 + l7 + ((lane >> 3) & 1) * 8) * 128 + (((c0 + (lane >> 4)) ^ l7) << 4));
      mma16816(o0, pa[2][0], pa[2][1], pa[3][0], pa[3][1], b[0], b[1]);
      mma16816(o1, pa[2][0], pa[2][1], pa[3][0], pa[3][1], b[2], b[3]);
    }
    {
      uint32_t b[2];
      ldsm_x2_t(b, Mb + 2048 + (np >> 2) * 1024 + l7 * 128 + (((c0 + ((lane >> 3) & 1)) ^ l7) << 4));
      mma1688(o0, pa[4][0], pa[4][1], b[0]);
      mma1688(o1, pa[4][0], pa[4][1], b[1]);
    }
    stsm_x4(qrow + (np >> 2) * 4096 + (((c0 + (lane >> 4)) ^ l7) << 4),
            pack_bf16(o0[0], o0[1]), pack_bf16(o0[2], o0[3]), pack_bf16(o1[0], o1[1]), pack_bf16(o1[2], o1[3]));
  }
  fence_async();
  __syncwarp();
  if (lane == 0) {
    tma_store_2d(omap, Qb + hf * 2048, ocol, orow + hf * 16);
    tma_store_2d(omap, Qb + 4096 + hf * 2048, ocol + 64, orow + hf * 16);
    asm volatile("cp.async.bulk.commit_group;" ::: "memory");
    asm volatile("cp.async.bulk.wait_group.read 0;" ::: "memory");
  }
}

__global__ void __launch_bounds__(384, 1) worker_kernel(const __grid_constant__ WorkerMaps maps) {
  extern __shared__ unsigned char smem_raw[];
  const uint32_t sb = (smem_u32(smem_raw) + 1023) & ~1023u;
  const uint32_t epi = sb + G_STAGES * G_STAGE_BYTES;
  const uint32_t bars = epi + G_EPI_BYTES;
  const uint32_t tfull = bars + 64, tempty = bars + 80, tslot = bars + 96, tdone = bars + 112;
  const uint32_t afull = bars + 128, aempty = bars + 128 + 8 * A_SLOTS;
  const int wg = threadIdx.x >> 7;
  if (threadIdx.x == 0) {
    for (int i = 0; i < G_STAGES; i++) { mbar_init(bars + 8 * i, 1); mbar_init(bars + 32 + 8 * i, 2); }
    for (int i = 0; i < 2; i++) { mbar_init(tfull + 8 * i, 1); mbar_init(tempty + 8 * i, 8); }
    for (int i = 0; i < A_SLOTS; i++) { mbar_init(afull + 8 * i, 1); mbar_init(aempty + 8 * i, 2); }
    sts32(tdone, 0);
    asm volatile("fence.mbarrier_init.release.cluster;" ::: "memory");
  }
  __syncthreads();
  if (wg == 2) {
    asm volatile("setmaxnreg.dec.sync.aligned.u32 40;");
    if (threadIdx.x == 256) {
      int st = 0; uint32_t ph = 1;
      const uint64_t evf = policy_evict_first();
      int as = 0; uint32_t aph = 1;
      bool amode = false;
      const bool att_class = atomicAdd(&g_ctrl.head[0][16], 1) % ACLASS == 0;
      for (uint32_t n = 0;; n++) {
        mbar_wait(tempty + 8 * (n & 1), ((n >> 1) & 1) ^ 1);
        const unsigned task = next_task(tdone, 8 * n, att_class);
        sts32(tslot + 4 * (n & 1), task);
        mbar_arrive(tfull + 8 * (n & 1));
        if (task == 0xFFFFFFFFu) break;
        asm volatile("fence.proxy.async;" ::: "memory");
        const unsigned kind = task >> 16, idx = task & 0xFFFF;
        if ((kind == 0) != amode) {
          if (amode) {
            for (int i = 0; i < A_SLOTS; i++) mbar_wait(aempty + 8 * i, aph ^ (i < as));
          } else {
            for (int i = 0; i < G_STAGES; i++) mbar_wait(bars + 32 + 8 * i, ph);
          }
          amode = !amode;
        }
        if (kind == 0) {
          int p, seg, h0, rounds;
          att_coords(idx, p, seg, h0, rounds);
          for (int u = 0; u < 4 * rounds; u++) {
            mbar_wait(aempty + 8 * as, aph);
            const uint32_t fb = afull + 8 * as, sa = sb + as * A_BYTES;
            mbar_expect(fb, A_BYTES);
            tma_load_4d_h(sa, &maps.qkv4, seg * SEG, (h0 + u) * 2, p * 3, fb, evf);
            tma_load_4d_h(sa + 24576, &maps.kvm4, 0, (h0 + u) * 2, (p * NSEG + seg) * 2, fb, evf);
            if (++as == A_SLOTS) { as = 0; aph ^= 1; }
          }
        } else if (kind == 3) {
          int tile, kb0, kb1;
          small_coords(idx, tile, kb0, kb1);
          const int arow = ((32 - NSMALL) * 2 + (tile >> 4)) * 64, bcol = (tile & 15) * 64;
          for (int kb = kb0; kb < kb1; kb++) {
            mbar_wait(bars + 32 + 8 * st, ph);
            const uint32_t fb = bars + 8 * st, sa = sb + st * G_STAGE_BYTES;
            mbar_expect(fb, 32768);
#pragma unroll
            for (int u = 0; u < 2; u++) {
              tma_load_2d(sa + u * 8192, &maps.o64, kb * 128 + u * 64, arow, fb);
              tma_load_2d(sa + 16384 + u * 8192, &maps.wo[1], bcol, kb * 128 + u * 64, fb);
            }
            if (++st == G_STAGES) { st = 0; ph ^= 1; }
          }
        } else {
          const CUtensorMap* ma = kind == 1 ? &maps.o128 : &maps.xb;
          int fblk, fw, fnb;
          filler_coords(kind == 2 ? idx : 0, fblk, fw, fnb);
          const int t = idx & 255, kq = kind == 1 ? idx >> 8 : 0, k0 = kq ? (kq - 1) * 1024 : 0;
          const CUtensorMap* mb = kind == 1 ? &maps.wo[t >> 6] : &maps.wb[fw];
          const int arow = kind == 1 ? (t >> 2) * 128 : fblk * 128;
          const int bcol = kind == 1 ? (t & 3) * 256 : fnb * 256;
          const int kblocks = kind == 1 && !kq ? 64 : 16;
          for (int kb = 0; kb < kblocks; kb++) {
            mbar_wait(bars + 32 + 8 * st, ph);
            const uint32_t fb = bars + 8 * st, sa = sb + st * G_STAGE_BYTES;
            mbar_expect(fb, G_STAGE_BYTES);
            tma_load_2d(sa, ma, k0 + kb * 64, arow, fb);
#pragma unroll
            for (int j = 0; j < 4; j++) tma_load_2d(sa + 16384 + j * 8192, mb, bcol + j * 64, k0 + kb * 64, fb);
            if (++st == G_STAGES) { st = 0; ph ^= 1; }
          }
        }
      }
    }
  } else {
    asm volatile("setmaxnreg.inc.sync.aligned.u32 232;");
    uint32_t ph = 0;
    const int tid = threadIdx.x & 127, warp = tid >> 5, lane = tid & 31;
    const uint32_t myepi = epi + wg * 16384;
    unsigned* pending = nullptr;
    unsigned pweight = 1, au = 0;
    auto flush = [&]() {
      if (pending) {
        asm volatile("cp.async.bulk.wait_group 0;" ::: "memory");
        asm volatile("red.relaxed.gpu.global.add.u32 [%0], %1;" ::"l"(pending), "r"(pweight) : "memory");
        pending = nullptr;
      }
    };
    for (uint32_t n = 0;; n++) {
      if (!mbar_test(tfull + 8 * (n & 1), (n >> 1) & 1)) flush();
      mbar_wait(tfull + 8 * (n & 1), (n >> 1) & 1);
      unsigned task;
      asm volatile("ld.shared.u32 %0, [%1];" : "=r"(task) : "r"(tslot + 4 * (n & 1)) : "memory");
      __syncwarp();
      if (lane == 0) mbar_arrive(tempty + 8 * (n & 1));
      if (task == 0xFFFFFFFFu) break;
      const unsigned kind = task >> 16, idx = task & 0xFFFF;
      if (kind == 0) {
        int p, seg, h0, rounds;
        att_coords(idx, p, seg, h0, rounds);
        const int pair = wg * 2 + (warp >> 1);
#pragma unroll 1
        for (int r = 0; r < rounds; r++) {
          const unsigned u = au + pair, slot = u % A_SLOTS;
          mbar_wait(afull + 8 * slot, (u / A_SLOTS) & 1);
          flush();
          attn_unit(sb + slot * A_BYTES, warp & 1, lane, &maps.o16, p * S_ + seg * SEG, (h0 + r * 4 + pair) * 128);
          if (lane == 0) mbar_arrive(aempty + 8 * slot);
          au += 4;
        }
        pweight = rounds;
        if (lane == 0) pending = &g_ctrl.o_ready[p * 32 + (seg >> 1)];
      } else if (kind == 3) {
        float d[32];
#pragma unroll
        for (int i = 0; i < 32; i++) d[i] = 0.f;
        int st = 0, prev = -1, tile, kb0, kb1;
        small_coords(idx, tile, kb0, kb1);
        const int nkb = idx < N_SM1 ? 32 : 32 / KSPLIT;
#pragma unroll 1
        for (int kb = 0; kb < nkb; kb++) {
          mbar_wait(bars + 8 * st, ph);
          const uint32_t sa = sb + st * G_STAGE_BYTES;
          asm volatile("wgmma.fence.sync.aligned;" ::: "memory");
#pragma unroll
          for (int k = 0; k < 4; k++)
            wgmma_n64(d, mkdesc(sa + wg * 8192 + k * 32, 16, 1024), mkdesc(sa + 16384 + wg * 8192 + k * 2048, 8192, 1024));
          asm volatile("wgmma.commit_group.sync.aligned;" ::: "memory");
          asm volatile("wgmma.wait_group.sync.aligned 1;" ::: "memory");
          if (prev >= 0 && tid == 0) mbar_arrive(bars + 32 + 8 * prev);
          if (kb == 0) flush();
          prev = st;
          if (++st == G_STAGES) { st = 0; ph ^= 1; }
        }
        asm volatile("wgmma.wait_group.sync.aligned 0;" ::: "memory");
        if (tid == 0) {
          mbar_arrive(bars + 32 + 8 * prev);
          asm volatile("cp.async.bulk.wait_group.read 0;" ::: "memory");
        }
        named_bar(1 + wg, 128);
        if (wg == 1) {
#pragma unroll
          for (int j = 0; j < 8; j++)
            sts128(myepi + j * 2048 + tid * 16, __float_as_uint(d[4 * j]), __float_as_uint(d[4 * j + 1]), __float_as_uint(d[4 * j + 2]), __float_as_uint(d[4 * j + 3]));
        }
        named_bar(3, 256);
        if (wg == 0) {
#pragma unroll
          for (int j = 0; j < 8; j++) {
            const uint4 v = lds128(epi + 16384 + j * 2048 + tid * 16);
            d[4 * j] += __uint_as_float(v.x); d[4 * j + 1] += __uint_as_float(v.y); d[4 * j + 2] += __uint_as_float(v.z); d[4 * j + 3] += __uint_as_float(v.w);
          }
          bool finish = true;
          if (KSPLIT > 1 && idx >= N_SM1) {
            unsigned* cnt = &g_ctrl.split[(tile & 15) * 2];
            if (tid == 0) sts32(tslot + 8, atomicAdd(cnt, 1));
            named_bar(1, 128);
            unsigned ord;
            asm volatile("ld.shared.u32 %0, [%1];" : "=r"(ord) : "r"(tslot + 8) : "memory");
            float4* part = g_part + (tile & 15) * (KSPLIT - 1) * 1024 + tid;
            finish = ord == KSPLIT - 1;
            if (!finish) {
#pragma unroll
              for (int j = 0; j < 8; j++) __stcg(part + ord * 1024 + j * 128, make_float4(d[4 * j], d[4 * j + 1], d[4 * j + 2], d[4 * j + 3]));
              named_bar(1, 128);
              if (tid == 0) red_release(cnt + 1);
            } else {
              for (unsigned n = 0; ld_acquire(cnt + 1) < KSPLIT - 1;)
                if (++n > (1u << 22)) __trap();
#pragma unroll
              for (int q = 0; q < KSPLIT - 1; q++)
#pragma unroll
                for (int j = 0; j < 8; j++) {
                  const float4 v = __ldcg(part + q * 1024 + j * 128);
                  d[4 * j] += v.x; d[4 * j + 1] += v.y; d[4 * j + 2] += v.z; d[4 * j + 3] += v.w;
                }
            }
          }
          if (finish) {
            const int row = warp * 16 + (lane & 7) + ((lane >> 3) & 1) * 8;
#pragma unroll
            for (int j = 0; j < 4; j++) {
              const float* s = d + j * 8;
              stsm_x4(myepi + row * 128 + (((j * 2 + (lane >> 4)) ^ (row & 7)) << 4),
                      pack_bf16(s[0], s[1]), pack_bf16(s[2], s[3]), pack_bf16(s[4], s[5]), pack_bf16(s[6], s[7]));
            }
            fence_async();
            named_bar(1, 128);
            if (tid == 0) {
              tma_store_2d(&maps.out, myepi, DM + (tile & 15) * 64, ((16 - NSMALL) * 2 + (tile >> 4)) * 64);
              asm volatile("cp.async.bulk.commit_group;" ::: "memory");
            }
          }
        }
        named_bar(3, 256);
      } else {
        const int t = idx & 255, kq = kind == 1 ? idx >> 8 : 0;
        const int kblocks = kind == 1 && !kq ? 64 : 16;
        float d[128];
#pragma unroll
        for (int i = 0; i < 128; i++) d[i] = 0.f;
        int st = 0, prev = -1;
        for (int kb = 0; kb < kblocks; kb++) {
          mbar_wait(bars + 8 * st, ph);
          const uint32_t sa = sb + st * G_STAGE_BYTES;
          asm volatile("wgmma.fence.sync.aligned;" ::: "memory");
#pragma unroll
          for (int k = 0; k < 4; k++)
            wgmma_n256(d, mkdesc(sa + wg * 8192 + k * 32, 16, 1024), mkdesc(sa + 16384 + k * 2048, 8192, 1024), (kb | k) != 0);
          asm volatile("wgmma.commit_group.sync.aligned;" ::: "memory");
          asm volatile("wgmma.wait_group.sync.aligned 1;" ::: "memory");
          if (prev >= 0 && tid == 0) mbar_arrive(bars + 32 + 8 * prev);
          if (kb == 1) flush();
          prev = st;
          if (++st == G_STAGES) { st = 0; ph ^= 1; }
        }
        asm volatile("wgmma.wait_group.sync.aligned 0;" ::: "memory");
        if (tid == 0) mbar_arrive(bars + 32 + 8 * prev);
        const CUtensorMap* mc = kind == 1 ? &maps.out : &maps.qkv64;
        int fblk, fw, fnb;
        filler_coords(kind == 2 ? idx : 0, fblk, fw, fnb);
        const int crow = kind == 1 ? ((t >> 2) & 15) * 128 : (3 + fw) * S_ + fblk * 128;
        const int ccol = kind == 1 ? (t >> 6) * DM + (t & 3) * 256 : fnb * 256;
        bool finish = true;
        if (kq) {
          unsigned* cnt = &g_ctrl.quart[((t - N_FULL) * 2 + wg) * 2];
          if (tid == 0) sts32(tslot + 8 + wg * 4, atomicAdd(cnt, 1));
          named_bar(1 + wg, 128);
          unsigned ord;
          asm volatile("ld.shared.u32 %0, [%1];" : "=r"(ord) : "r"(tslot + 8 + wg * 4) : "memory");
          float4* park = g_park + (size_t)((t - N_FULL) * 2 + wg) * 3 * 4096 + tid;
          finish = ord == 3;
          if (!finish) {
#pragma unroll
            for (int j = 0; j < 32; j++) __stcg(park + ord * 4096 + j * 128, make_float4(d[4 * j], d[4 * j + 1], d[4 * j + 2], d[4 * j + 3]));
            named_bar(1 + wg, 128);
            if (tid == 0) red_release(cnt + 1);
          } else {
            for (unsigned n = 0; ld_acquire(cnt + 1) < 3;)
              if (++n > (1u << 22)) __trap();
#pragma unroll 1
            for (int q = 0; q < 3; q++)
#pragma unroll
              for (int j = 0; j < 32; j++) {
                const float4 v = __ldcg(park + q * 4096 + j * 128);
                d[4 * j] += v.x; d[4 * j + 1] += v.y; d[4 * j + 2] += v.z; d[4 * j + 3] += v.w;
              }
          }
        }
#pragma unroll
        for (int hf = 0; hf < 2; hf++) {
          if (!finish) break;
          if (tid == 0) asm volatile("cp.async.bulk.wait_group.read 0;" ::: "memory");
          named_bar(1 + wg, 128);
          const int row = warp * 16 + (lane & 7) + ((lane >> 3) & 1) * 8;
#pragma unroll
          for (int j = 0; j < 8; j++) {
            const float* s = d + hf * 64 + j * 8;
            const int chunk = (j & 3) * 2 + (lane >> 4);
            stsm_x4(myepi + (j >> 2) * 8192 + row * 128 + ((chunk ^ (row & 7)) << 4),
                    pack_bf16(s[0], s[1]), pack_bf16(s[2], s[3]), pack_bf16(s[4], s[5]), pack_bf16(s[6], s[7]));
          }
          fence_async();
          named_bar(1 + wg, 128);
          if (tid == 0) {
            const uint64_t evf = policy_evict_first();
            tma_store_2d_h(mc, myepi, ccol + hf * 128, crow + wg * 64, evf);
            tma_store_2d_h(mc, myepi + 8192, ccol + hf * 128 + 64, crow + wg * 64, evf);
            asm volatile("cp.async.bulk.commit_group;" ::: "memory");
          }
        }
        pweight = 1;
        if (kind == 2 && tid == 0) pending = fw == 0 ? &g_ctrl.q_ready[fblk / FG] : &g_ctrl.kvx_ready[fblk / FG];
      }
      if (lane == 0) asm volatile("red.shared.add.u32 [%0], 1;" ::"r"(tdone) : "memory");
    }
    flush();
    if (lane == 0) asm volatile("cp.async.bulk.wait_group 0;" ::: "memory");
  }
}

struct ChainParams {
  CUtensorMap kv;
  CUtensorMap kvm;
  const bf16* wq[2]; const bf16* wk[2]; const bf16* wv[2]; const bf16* wo[2]; const bf16* mem0[2];
};
#define NSM_TILES 32
#define NPF_TILES 12
#define NWO_RES 3
#define PRE_LO 1
#define PRE_HI 3
#define LOOKAHEAD 4
#define DELAY1 400
#define DELAY2 200
#define DELAY3 60
#define DELAY4 40
#define NPROBE 6
#define RL1 2
#define RL2 3
constexpr int NST = NSM_TILES, NRT = 64 - NST, NPF = NPF_TILES, NWR = NWO_RES;
constexpr int NSG = NST / 4;
static_assert(NST % 4 == 0, "whole groups");
constexpr int NPG = NPF / 4;
__host__ __device__ constexpr int smem_before(int gi) { return gi <= NPG ? gi : NPG + ((gi - NPG) * (NSG - NPG)) / (16 - NPG); }
__host__ __device__ constexpr bool in_smem(int i) { return smem_before((i >> 2) + 1) != smem_before(i >> 2); }
__host__ __device__ constexpr int smem_slot(int i) { return smem_before(i >> 2) * 4 + (i & 3); }
__host__ __device__ constexpr int reg_slot(int i) { return i - smem_before(i >> 2) * 4; }
constexpr int C_KV = 0;
constexpr int C_WS = C_KV + 12288;
constexpr int C_WO = C_WS + 8 * NST * 512;
constexpr int C_RED = C_WO + (8 - NWR) * 22 * 512;
constexpr int C_QK = (C_RED + 4 * 8 * 544 + 1023) / 1024 * 1024;
constexpr int C_VM = C_QK + 2048;
constexpr int C_SC = C_VM + 2048;
constexpr int C_OB = C_SC + 2560;
constexpr int C_SENT = C_OB + 2560;
constexpr int C_BAR = C_SENT + 2048;
constexpr int C_TAB = C_BAR + 64;
constexpr int C_SMEM = C_TAB + 1536;
static_assert(C_SMEM <= 232448 && C_QK % 1024 == 0, "smem");
constexpr uint32_t SENT = 0xFFFFFFFFu;
#define F_(x) __uint_as_float(x)

__device__ __forceinline__ uint32_t pin(uint32_t x) {
  return __shfl_sync(~0u, x, threadIdx.x & 31);
}
__device__ __forceinline__ void spin(uint32_t t0, uint32_t d) {
  asm volatile("{\n.reg .pred p;\n.reg .u32 t;\nSPIN:\nmov.u32 t, %clock;\nsub.u32 t, t, %0;\nsetp.lt.u32 p, t, %1;\n@p bra.uni SPIN;\n}\n" ::"r"(t0), "r"(d));
}
__device__ __forceinline__ uint4 ldg128(const void* p) {
  uint4 v;
  asm volatile("ld.global.nc.L1::no_allocate.v4.u32 {%0,%1,%2,%3}, [%4];" : "=r"(v.x), "=r"(v.y), "=r"(v.z), "=r"(v.w) : "l"(p));
  return v;
}
__device__ __forceinline__ uint32_t ldg32(const void* p) {
  uint32_t v;
  asm volatile("ld.global.nc.L1::no_allocate.u32 %0, [%1];" : "=r"(v) : "l"(p));
  return v;
}
__device__ __forceinline__ float2 lds64(uint32_t a) {
  float2 v;
  asm volatile("ld.shared.v2.f32 {%0,%1}, [%2];" : "=f"(v.x), "=f"(v.y) : "r"(a));
  return v;
}
__device__ __forceinline__ void bulk_s2g(void* dst, uint32_t src, uint32_t bytes) {
  asm volatile("cp.async.bulk.global.shared::cta.bulk_group [%0], [%1], %2;" ::"l"(dst), "r"(src), "r"(bytes) : "memory");
}
template <int N>
__device__ __forceinline__ void polln(uint4* v, const unsigned char* src) {
#pragma unroll
  for (int i = 0; i < N; i++) v[i] = ld_relaxed4(src + i * 512);
  uint32_t n = 0;
  while (true) {
    uint32_t mi[N], m = 0;
#pragma unroll
    for (int i = 0; i < N; i++) mi[i] = __vimax3_u32(__vimax3_u32(v[i].x, v[i].y, v[i].z), v[i].w, 0u);
#pragma unroll
    for (int i = 0; i < N; i += 2) m = __vimax3_u32(m, mi[i], mi[i + 1]);
    const bool bad = __any_sync(~0u, m == SENT);
    if (!bad) break;
#pragma unroll
    for (int i = 0; i < N; i++)
      if (mi[i] == SENT) v[i] = ld_relaxed4(src + i * 512);
    if (++n > (1u << 22)) __trap();
  }
}
template <int PRE, bool COND3>
__device__ __forceinline__ void wo_prefetch(uint4 (*wo)[8], uint32_t a, bool has3) {
#pragma unroll
  for (int ks = NWR; ks < NWR + PRE && ks < 8; ks++) {
    wo[0][ks] = lds128(a + (ks - NWR) * 11264);
    wo[1][ks] = lds128(a + (ks - NWR) * 11264 + 4096);
    if (COND3) wo[2][ks] = make_uint4(0, 0, 0, 0);
    if (!COND3 || has3) wo[2][ks] = lds128(a + (ks - NWR) * 11264 + 8192);
  }
}
template <int PRE, bool COND3>
__device__ __forceinline__ void wo_phase(uint4 (*wo)[8], const uint32_t (*wres)[4], uint32_t a, uint32_t oa, bool has3,
                                         unsigned char* dst, uint32_t sel) {
  uint4 ob[4];
#pragma unroll
  for (int t = 0; t < 4; t++) ob[t] = lds128(oa + t * 64);
  float acc[3][4];
#pragma unroll
  for (int j = 0; j < 3; j++) acc[j][0] = acc[j][1] = acc[j][2] = acc[j][3] = 0.f;
#pragma unroll
  for (int kn = NWR + PRE; kn < LOOKAHEAD; kn++) {
    wo[0][kn] = lds128(a + (kn - NWR) * 11264);
    wo[1][kn] = lds128(a + (kn - NWR) * 11264 + 4096);
    if (COND3) wo[2][kn] = make_uint4(0, 0, 0, 0);
    if (!COND3 || has3) wo[2][kn] = lds128(a + (kn - NWR) * 11264 + 8192);
  }
  constexpr int LA = NWR + PRE > LOOKAHEAD ? NWR + PRE : LOOKAHEAD;
#pragma unroll
  for (int ks = 0; ks < 8; ks++) {
    if (ks + LA < 8) {
      const int kn = ks + LA < 8 ? ks + LA : 0;
      wo[0][kn] = lds128(a + (kn - NWR) * 11264);
      wo[1][kn] = lds128(a + (kn - NWR) * 11264 + 4096);
      if (COND3) wo[2][kn] = make_uint4(0, 0, 0, 0);
      if (!COND3 || has3) wo[2][kn] = lds128(a + (kn - NWR) * 11264 + 8192);
    }
    uint32_t b0 = (ks & 1) ? ob[ks >> 1].z : ob[ks >> 1].x, b1 = (ks & 1) ? ob[ks >> 1].w : ob[ks >> 1].y;
#pragma unroll
    for (int j = 0; j < 3; j++) {
      if (ks < NWR) { const uint32_t* r = wres[ks < NWR ? ks * 3 + j : 0]; mma16816(acc[j], r[0], r[1], r[2], r[3], b0, b1); }
      else mma16816(acc[j], wo[j][ks].x, wo[j][ks].y, wo[j][ks].z, wo[j][ks].w, b0, b1);
    }
  }
#pragma unroll
  for (int j = 0; j < 3; j++)
    if (j < 2 || !COND3 || has3)
      st_relaxed2(dst + (size_t)j * 48 * MB_BLK + (((sel >> j) & 1) << 12), pack_bf16(acc[j][0], acc[j][2]), pack_bf16(acc[j][1], acc[j][3]));
}

template <bool QK>
__device__ __forceinline__ void chain_body(const ChainParams& P, const uint32_t sb, const int rank, const int h) {
  const int bid = h * 3 + rank;
  const int warp = __shfl_sync(~0u, threadIdx.x >> 5, 0), lane = threadIdx.x & 31, g = lane >> 2, c = lane & 3;
  const uint32_t barX = sb + C_BAR, barF = sb + C_BAR + 8, barR = sb + C_BAR + 16;
  constexpr uint32_t xbytes = 2560 + (QK ? 2048 : 0);
  constexpr uint32_t kvbytes = QK ? 12288 : 8192;
  const int wslot = (warp + 4) & 7;
  const int gw = wslot * 3 + rank;
  const bool has3 = gw < 16;
  const int unit = bid + 96 * (warp - 5);
  const bool reducer = warp == 5 || (warp == 6 && bid < 32);
  uint32_t fph = 0;
  int xi = 0;
  uint32_t near2, near1;
  {
    uint32_t nb;
    asm volatile("ld.shared.u32 %0, [%1];" : "=r"(nb) : "r"(sb + C_BAR + 32));
    nb = __shfl_sync(~0u, nb, 0);
    near2 = (nb >> (warp >> 1)) & 1;
    near1 = (nb >> (4 + (warp == 6))) & 1;
  }
  const uint32_t u1 = unit * MB_BLK + near1 * 4096;
  const uint32_t u2 = (128 + (warp >> 1)) * MB_BLK + near2 * 4096 + (warp & 1) * 2048;
  const uint32_t u3 = (128 + (unit >> 5)) * MB_BLK + ((unit >> 2) & 7) * 512 + (unit & 1) * 256 + ((unit >> 1) & 1) * 32;
  const uint32_t l16 = pin(lane * 16);
  if (warp == 0) {
    const int l7 = lane & 7;
    sts128(sb + C_TAB + l16,
           (2 * (g & 3) * 128 + (((2 * (c >> 1) + (g >> 2)) ^ (2 * (g & 3))) << 4) + (c & 1) * 4) | ((l7 * 128 + (((lane >> 3) ^ l7) << 4)) << 16),
           (l7 * 128 + ((((lane >> 4) | ((lane >> 2) & 2)) ^ l7) << 4)) | ((c * 544 + g * 16) << 16),
           ((l7 + (lane >> 4) * 8) * 128 + ((((lane >> 3) & 1) ^ l7) << 4)) | ((2 * c * 320 + g * 4) << 16),
           g * 320 + c * 16);
  }
  const uint32_t sendw = (warp < 5) | ((warp == 4) << 1);
#define lqw (((tw0 & 0xFFFF) ^ ((warp & 1) * 64)) + ((warp >> 2) * 1024 + ((warp >> 1) & 1) * 8))
#define lqr (tw0 >> 16)
#define lka (tw1 & 0xFFFF)
#define lrd (tw1 >> 16)
#define lva ((tw2 & 0xFFFF) ^ ((warp & 1) * 64))
#define lvm ((lqr ^ ((warp & 1) * 64)) + ((warp >> 1) & 1) * 1024)
#define low (tw2 >> 16)
#define lor tw3
#define l1 (pk2 & ~7u)
#define SEL(n) (g == (n) ? 0x00003F80u : g == (n) + 1 ? 0x3F800000u : 0u)
  const uint32_t aB = sb + warp * 512 + l16, aW = sb + C_WO + wslot * 512 + l16;

  auto store_kv = [&](int p, int s) {
    if (QK) {
      tma_store_2d(&P.kvm, sb + C_QK + 1024, h * 128 + rank * 64, (p * NSEG + s) * 16);
    } else {
      tma_store_2d(&P.kvm, sb + C_QK, h * 128, (p * NSEG + s) * 16 + 8);
      tma_store_2d(&P.kvm, sb + C_QK + 1024, h * 128 + 64, (p * NSEG + s) * 16 + 8);
    }
    asm volatile("cp.async.bulk.commit_group;" ::: "memory");
    asm volatile("cp.async.bulk.wait_group 0;" ::: "memory");
    asm volatile("red.relaxed.gpu.global.add.u32 [%0], 1;" ::"l"(&g_ctrl.kv_ready[p * NSEG + s]) : "memory");
  };
  auto issue_kv = [&](int p, int s) {
    if (K1_KV < 512 && p == 1 && s % (4 * FG) == 0 && fil_kv(s / (4 * FG)) > 0) {
      for (uint32_t n = 0; ld_acquire(&g_ctrl.kvx_ready[s / (4 * FG)]) < 2 * fil_kv(s / (4 * FG));)
        if (++n > (1u << 22)) __trap();
      asm volatile("fence.proxy.async;" ::: "memory");
    }
    mbar_expect(barF, kvbytes);
    if (QK) tma_load_2d(sb + C_KV, &P.kv, h * 128 + rank * 64, (p * 3 + 1) * S_ + s * SEG, barF);
    tma_load_2d(sb + C_KV + 4096, &P.kv, h * 128, (p * 3 + 2) * S_ + s * SEG, barF);
    tma_load_2d(sb + C_KV + 8192, &P.kv, h * 128 + 64, (p * 3 + 2) * S_ + s * SEG, barF);
  };

#pragma unroll 1
  for (int p = 0; p < 2; p++) {
    if (p == 1 && threadIdx.x == 0) issue_kv(p, 0);
    uint32_t wr[NRT][4];
    uint32_t wres[NWR > 0 ? NWR * 3 : 1][4];
    {
      const bf16* w0 = (QK ? P.wq[p] + h * 128 + rank * 64 : P.wv[p] + h * 128) + (size_t)(warp * 128 + c * 8) * HD + g * 8;
      const bf16* w1 = (QK ? P.wk[p] + h * 128 + rank * 64 : P.wv[p] + h * 128 + 64) + (size_t)(warp * 128 + c * 8) * HD + g * 8;
      auto frag = [](const uint4* x, int j, uint32_t* a) {
        uint32_t x0 = j == 0 ? x[0].x : j == 1 ? x[0].y : j == 2 ? x[0].z : x[0].w;
        uint32_t x1 = j == 0 ? x[1].x : j == 1 ? x[1].y : j == 2 ? x[1].z : x[1].w;
        uint32_t x2 = j == 0 ? x[2].x : j == 1 ? x[2].y : j == 2 ? x[2].z : x[2].w;
        uint32_t x3 = j == 0 ? x[3].x : j == 1 ? x[3].y : j == 2 ? x[3].z : x[3].w;
        a[0] = __byte_perm(x0, x1, 0x5410); a[1] = __byte_perm(x0, x1, 0x7632);
        a[2] = __byte_perm(x2, x3, 0x5410); a[3] = __byte_perm(x2, x3, 0x7632);
      };
      {
        uint4 x[NSG][4];
        uint32_t y[3][8][4];
#pragma unroll
        for (int gi = 0; gi < 16; gi++)
          if (in_smem(gi * 4)) {
#pragma unroll
            for (int i = 0; i < 4; i++)
              x[smem_slot(gi * 4) >> 2][i] = ldg128(((gi & 1) ? w1 : w0) + (size_t)((gi >> 2) * 32 + ((gi >> 1) & 1) * 4 + i) * HD);
          }
#pragma unroll
        for (int j = 0; j < 3; j++) {
          const bf16* wb = P.wo[p] + (size_t)(h * 128 + (c >> 1) * 16 + (c & 1) * 4) * DM + ((gw + 24 * j) & 63) * 16 + g * 2;
#pragma unroll
          for (int ks = 0; ks < 8; ks++)
#pragma unroll
            for (int i = 0; i < 4; i++)
              y[j][ks][i] = ldg32(wb + (size_t)((ks >> 1) * 32 + (ks & 1) * 2 + (i >> 1) + (i & 1) * 8) * DM);
        }
#pragma unroll
        for (int t = 0; t < NST; t++) {
          uint32_t a[4];
          frag(x[t >> 2], t & 3, a);
          sts128(aB + C_WS + t * 4096, a[0], a[1], a[2], a[3]);
        }
#pragma unroll
        for (int j = 0; j < 3; j++)
#pragma unroll
          for (int ks = 0; ks < 8; ks++) {
            const uint32_t* x = y[j][ks];
            uint32_t a0 = __byte_perm(x[0], x[1], 0x5410), a1 = __byte_perm(x[0], x[1], 0x7632);
            uint32_t a2 = __byte_perm(x[2], x[3], 0x5410), a3 = __byte_perm(x[2], x[3], 0x7632);
            if (ks < NWR) { uint32_t* r = wres[ks < NWR ? ks * 3 + j : 0]; r[0] = a0; r[1] = a1; r[2] = a2; r[3] = a3; }
            else if (j < 2 || has3) sts128(aW + (ks - NWR) * 11264 + j * 4096, a0, a1, a2, a3);
          }
      }
      {
        uint4 x[16 - NSG][4];
#pragma unroll
        for (int gi = 0; gi < 16; gi++)
          if (!in_smem(gi * 4)) {
#pragma unroll
            for (int i = 0; i < 4; i++)
              x[reg_slot(gi * 4) >> 2][i] = ldg128(((gi & 1) ? w1 : w0) + (size_t)((gi >> 2) * 32 + ((gi >> 1) & 1) * 4 + i) * HD);
          }
#pragma unroll
        for (int t = 0; t < NRT; t++) frag(x[t >> 2], t & 3, wr[t]);
      }
      __syncwarp();
    }
    if (p == 0) {
      if (threadIdx.x < 128) {
        for (uint32_t n = 0; ld_acquire(&g_ctrl.place[threadIdx.x]) == 0;)
          if (++n > (1u << 22)) __trap();
      }
      __syncthreads();
      uint32_t pk2 = gw * 2 * MB_BLK + h * 128 + (c >> 1) * MB_BLK + (c & 1) * 64 + g * 8;
#pragma unroll
      for (int j = 0; j < 3; j++)
        if (j < 2 || has3) pk2 |= (ld_relaxed1(&g_ctrl.place[(gw + 24 * j) * 2 + (c >> 1)]) - 1) << j;
      sts32(sb + C_TAB + 512 + threadIdx.x * 4, pk2);
      if (threadIdx.x == 0) {
        asm volatile("griddepcontrol.wait;" ::: "memory");
        issue_kv(p, 0);
      }
    }
#pragma unroll 1
    for (int s = 0; s < NSEG; s++) {
      uint4 bw[4];
      uint4 pf[NPF > 0 ? NPF : 1];
#pragma unroll
      for (int i = 0; i < NPF; i++) pf[i] = lds128(aB + C_WS + i * 4096);
      mbar_wait_u(barF, fph);
      fph ^= 1;
      if (s == 0) {
        const bf16* m0 = P.mem0[p] + g * DM + warp * 128 + c * 8;
#pragma unroll
        for (int t = 0; t < 4; t++) bw[t] = __ldg((const uint4*)(m0 + t * 32));
      } else {
        const unsigned char* src = g_mb + (uint32_t)(u2 + ((xi - 1) & (RING - 1)) * MB_SLOT + l16);
        mbar_wait_u(barR, (xi - 1) & 1);
        if (DELAY2 > 0) spin(clock(), DELAY2);
        polln<4>(bw, src);
      }
      uint32_t tw0, tw1;
      {
        float acc[8][4];
#pragma unroll
        for (int j = 0; j < 8; j++) acc[j][0] = acc[j][1] = acc[j][2] = acc[j][3] = 0.f;
#pragma unroll
        for (int ks = 0; ks < 8; ks++) {
          uint32_t b0 = (ks & 1) ? bw[ks >> 1].z : bw[ks >> 1].x, b1 = (ks & 1) ? bw[ks >> 1].w : bw[ks >> 1].y;
#pragma unroll
          for (int j = 0; j < 8; j++) {
            const int i = ks * 8 + j;
            if (!in_smem(i)) {
              const uint32_t* a = wr[in_smem(i) ? 0 : reg_slot(i)];
              mma16816(acc[j], a[0], a[1], a[2], a[3], b0, b1);
            } else {
              uint4 a = smem_slot(i) < NPF ? pf[smem_slot(i) < NPF ? smem_slot(i) : 0] : lds128(aB + C_WS + smem_slot(i) * 4096);
              mma16816(acc[j], a.x, a.y, a.z, a.w, b0, b1);
            }
          }
        }
        const float2 tab = lds64(sb + C_TAB + l16);
        tw0 = __float_as_uint(tab.x); tw1 = __float_as_uint(tab.y);
#pragma unroll
        for (int j = 0; j < 4; j++)
          sts128(sb + C_RED + warp * 544 + j * 4352 + l16, pack_bf16(acc[2 * j][0], acc[2 * j][2]), pack_bf16(acc[2 * j][1], acc[2 * j][3]),
                 pack_bf16(acc[2 * j + 1][0], acc[2 * j + 1][2]), pack_bf16(acc[2 * j + 1][1], acc[2 * j + 1][3]));
      }
      uint32_t kf[8] = {0, 0, 0, 0, 0, 0, 0, 0};
      const uint32_t ka = sb + (warp < 4 ? C_KV + warp * 1024 : C_QK + 1024) + lka;
      if (QK) {
        ldsm_x4_if(kf, ka, warp < 4);
        ldsm_x4_if(kf + 4, ka ^ 64, warp < 4);
      }
      __syncthreads();
      {
        const uint32_t ra = sb + C_RED + (warp >> 1) * 4352 + (warp & 1) * 256 + lrd;
        uint4 v0 = lds128(ra), v1 = lds128(ra + 128), v2 = lds128(ra + 2176), v3 = lds128(ra + 2176 + 128);
        float d0[4] = {0.f, 0.f, 0.f, 0.f}, d1[4] = {0.f, 0.f, 0.f, 0.f};
        mma16816(d0, v0.x, v0.y, v0.z, v0.w, SEL(0), SEL(2));
        mma16816(d1, v2.x, v2.y, v2.z, v2.w, SEL(0), SEL(2));
        mma16816(d0, v1.x, v1.y, v1.z, v1.w, SEL(4), SEL(6));
        mma16816(d1, v3.x, v3.y, v3.z, v3.w, SEL(4), SEL(6));
        sts32(sb + C_QK + lqw, pack_bf16(d0[0] + d1[0], d0[1] + d1[1]));
        sts32(sb + C_QK + 128 + (lqw ^ 16), pack_bf16(d0[2] + d1[2], d0[3] + d1[3]));
      }
      const bool last = s == NSEG - 1;
      uint32_t ra[3], rb[3], send = (sendw & 1) && !last, km = sendw >> 1;
      if (QK) {
#pragma unroll
        for (int r = 0; r < 3; r++) {
          ra[r] = mapa(sb + C_SC + rank * 1280 + warp * 256 + (l16 >> 1), r);
          rb[r] = mapa(barX, r);
          asm volatile("" : "+r"(ra[r]), "+r"(rb[r]));
        }
        asm volatile("" : "+r"(send), "+r"(km));
      }
      if (!QK) fence_async();
      __syncthreads();
      if (QK) {
        uint32_t qf[8] = {0, 0, 0, 0, 0, 0, 0, 0};
        ldsm_x4_if(qf, sb + C_QK + lqr, send);
        ldsm_x4_if(qf + 4, sb + C_QK + (lqr ^ 64), send);
        ldsm_x4_if(kf, ka, km);
        ldsm_x4_if(kf + 4, ka ^ 64, km);
        float sa[4][4];
#pragma unroll
        for (int i = 0; i < 4; i++) {
          sa[i][0] = sa[i][1] = sa[i][2] = sa[i][3] = 0.f;
          const uint32_t* q = qf + (i >> 1) * 4;
          mma16816(sa[i], q[0], q[1], q[2], q[3], kf[2 * i], kf[2 * i + 1]);
        }
        float s0 = (sa[0][0] + sa[1][2]) + (sa[2][0] + sa[3][2]), s1 = (sa[0][1] + sa[1][3]) + (sa[2][1] + sa[3][3]);
        if (send)
          asm volatile("st.async.shared::cluster.mbarrier::complete_tx::bytes.v2.f32 [%2], {%0, %1}, [%3];\n"
                       "st.async.shared::cluster.mbarrier::complete_tx::bytes.v2.f32 [%4], {%0, %1}, [%5];\n"
                       "st.async.shared::cluster.mbarrier::complete_tx::bytes.v2.f32 [%6], {%0, %1}, [%7];"
                       ::"f"(s0), "f"(s1), "r"(ra[0]), "r"(rb[0]), "r"(ra[1]), "r"(rb[1]), "r"(ra[2]), "r"(rb[2]) : "memory");
        fence_async();
      } else {
        if (warp < 2) {
          if (lane == 0 && !last)
            asm volatile("cp.async.bulk.shared::cluster.shared::cta.mbarrier::complete_tx::bytes [%0], [%1], %2, [%3];"
                         ::"r"(mapa(sb + C_VM, warp)), "r"(sb + C_QK), "r"(2048), "r"(mapa(barX, warp)) : "memory");
        }
      }
      if (last) {
        __syncthreads();
        if (threadIdx.x == 224) store_kv(p, s);
        __syncthreads();
        break;
      }
      const float2 tab = lds64(sb + C_TAB + 8 + l16);
      const uint32_t tw2 = __float_as_uint(tab.x), tw3 = __float_as_uint(tab.y);
      uint32_t pk2;
      asm volatile("ld.shared.u32 %0, [%1];" : "=r"(pk2) : "r"(sb + C_TAB + 512 + warp * 128 + (l16 >> 2)));
      unsigned char* dst = g_mb + (uint32_t)((xi & (RING - 1)) * MB_SLOT + l1);
      uint4 wo[3][8];
      if (warp < 4) {
        if (!QK) spin(clock(), DELAY3);
        uint32_t vf[16];
        {
          uint32_t va = sb + C_KV + 4096 + (warp >> 1) * 4096 + lva;
          ldsm_x4_t(vf, va);
          ldsm_x4_t(vf + 4, va + 2048);
          ldsm_x4_t(vf + 8, va ^ 32);
          ldsm_x4_t(vf + 12, (va ^ 32) + 2048);
        }
        wo_prefetch<PRE_LO, true>(wo, aW, has3);
        const uint32_t vma = sb + (QK ? C_VM : C_QK) + lvm;
        mbar_wait_u(barX, xi & 1);
        const float sc = 0.08838834764831845f * 1.4426950408889634f;
        float2 qa[5], qb[5];
#pragma unroll
        for (int i = 0; i < 5; i++) {
          qa[i] = lds64(sb + C_SC + i * 256 + (l16 >> 1));
          qb[i] = lds64(sb + C_SC + 1280 + i * 256 + (l16 >> 1));
        }
        uint32_t vm[4];
        ldsm_x4_t(vm, vma);
        float sv[10];
#pragma unroll
        for (int i = 0; i < 5; i++) { sv[2 * i] = qa[i].x + qb[i].x; sv[2 * i + 1] = qa[i].y + qb[i].y; }
        float m = fmaxf(fmaxf(fmaxf(fmaxf(sv[0], sv[1]), fmaxf(sv[2], sv[3])), fmaxf(fmaxf(sv[4], sv[5]), fmaxf(sv[6], sv[7]))), fmaxf(sv[8], sv[9]));
        m = fmaxf(m, __shfl_xor_sync(~0u, m, 1)); m = fmaxf(m, __shfl_xor_sync(~0u, m, 2));
        const float ms = -m * sc;
        uint32_t pa[5];
#pragma unroll
        for (int nt = 0; nt < 5; nt++) pa[nt] = pack_bf16(ex2(fmaf(sv[2 * nt], sc, ms)), ex2(fmaf(sv[2 * nt + 1], sc, ms)));
        const uint32_t one2 = 0x3F803F80u;
        float o[3][2][4];
#pragma unroll
        for (int i = 0; i < 4; i++) o[0][0][i] = o[0][1][i] = o[1][0][i] = o[1][1][i] = o[2][0][i] = o[2][1][i] = 0.f;
        mma16816(o[2][0], one2, one2, one2, one2, pa[0], pa[1]);
        mma16816(o[0][0], vf[0], vf[1], vf[2], vf[3], pa[0], pa[1]);
        mma16816(o[1][0], vf[8], vf[9], vf[10], vf[11], pa[0], pa[1]);
        mma16816(o[2][1], one2, one2, one2, one2, pa[2], pa[3]);
        mma16816(o[0][1], vf[4], vf[5], vf[6], vf[7], pa[2], pa[3]);
        mma16816(o[1][1], vf[12], vf[13], vf[14], vf[15], pa[2], pa[3]);
        mma1688(o[2][0], one2, one2, pa[4]);
        mma1688(o[0][0], vm[0], vm[1], pa[4]);
        mma1688(o[1][0], vm[2], vm[3], pa[4]);
        float i0, i1;
        asm("rcp.approx.ftz.f32 %0, %1;" : "=f"(i0) : "f"(o[2][0][0] + o[2][1][0]));
        asm("rcp.approx.ftz.f32 %0, %1;" : "=f"(i1) : "f"(o[2][0][1] + o[2][1][1]));
#pragma unroll
        for (int t = 0; t < 2; t++) {
          sts32(sb + C_OB + warp * 64 + t * 32 + low, pack_bf16((o[t][0][0] + o[t][1][0]) * i0, (o[t][0][2] + o[t][1][2]) * i0));
          sts32(sb + C_OB + warp * 64 + t * 32 + 320 + low, pack_bf16((o[t][0][1] + o[t][1][1]) * i1, (o[t][0][3] + o[t][1][3]) * i1));
        }
        __syncthreads();
        wo_phase<PRE_LO, true>(wo, wres, aW, sb + C_OB + lor, has3, dst, pk2);
      } else {
        if (!QK || DELAY4 > 0) spin(clock(), QK ? DELAY4 : DELAY3);
        wo_prefetch<PRE_HI, false>(wo, aW, true);
        if (warp == 7 && xi >= RL1 && lane < 6) {
          uint32_t nb;
          asm volatile("ld.shared.u32 %0, [%1];" : "=r"(nb) : "r"(sb + C_BAR + 32));
          unsigned char* b1 = g_mb + (size_t)(bid + (lane >> 1) * 96) * MB_BLK + ((xi - RL1) & (RING - 1)) * MB_SLOT +
                              ((nb >> (4 + (lane >> 1))) & 1) * 4096 + (lane & 1) * 2048;
          unsigned char* b2 = g_mb + (size_t)(128 + (bid >> 3)) * MB_BLK + ((xi - RL2) & (RING - 1)) * MB_SLOT + (lane & 1) * 4096 + (bid & 7) * 512;
          if (lane < 2 || (bid < 32 && (lane < 4 || xi >= RL2))) bulk_s2g(lane < 4 ? b1 : b2, sb + C_SENT, lane < 4 ? 2048 : 512);
          asm volatile("cp.async.bulk.commit_group;" ::: "memory");
        }
        __syncthreads();
        wo_phase<PRE_HI, false>(wo, wres, aW, sb + C_OB + lor, true, dst, pk2);
      }
      const uint32_t tsent = clock();
      if (reducer) {
        const unsigned char* src = g_mb + (uint32_t)(u1 + (xi & (RING - 1)) * MB_SLOT + ((l16 & 48) * 8 + (l16 >> 6) * 16));
        unsigned char* o = g_mb + (uint32_t)(u3 + (xi & (RING - 1)) * MB_SLOT + ((l16 >> 8) * 128 + ((l16 >> 3) & 24) + ((l16 >> 2) & 12)));
        const uint32_t sel0 = SEL(0), sel1 = SEL(2);
        spin(tsent, DELAY1);
        uint4 v[8];
        polln<8>(v, src);
        float d[4][4];
#pragma unroll
        for (int i = 0; i < 4; i++) {
          d[i][0] = d[i][1] = d[i][2] = d[i][3] = 0.f;
          mma16816(d[i], v[i].x, v[i].y, v[i].z, v[i].w, sel0, sel1);
        }
#pragma unroll
        for (int i = 0; i < 4; i++) mma16816(d[i], v[4 + i].x, v[4 + i].y, v[4 + i].z, v[4 + i].w, sel0, sel1);
#pragma unroll
        for (int i = 0; i < 4; i++) d[0][i] = (d[0][i] + d[1][i]) + (d[2][i] + d[3][i]);
        uint32_t w0 = pack_bf16(d[0][0], d[0][1]), w1 = pack_bf16(d[0][2], d[0][3]);
        w0 = __shfl_sync(~0u, w0, lane & ~2); w1 = __shfl_sync(~0u, w1, lane & ~2);
        o += (c >> 1) * (4096 - 8);
        st_relaxed1(o, w0);
        st_relaxed1(o + 64, w1);
        if (warp == 5 && lane == 0) mbar_arrive(barR);
      } else if (warp == 7) {
        if (lane == 0) store_kv(p, s);
        else asm volatile("cp.async.bulk.wait_group 0;" ::: "memory");
      } else if (warp == 4 && lane == 0) {
        mbar_expect(barX, xbytes);
        issue_kv(p, s + 1);
      }
      xi++;
    }
  }
}

__global__ void __launch_bounds__(256, 1) chain_kernel(const __grid_constant__ ChainParams P) {
  extern __shared__ __align__(1024) unsigned char smem_raw[];
  const uint32_t sb = smem_u32(smem_raw);
  const int rank = blockIdx.x % 3;
  const int warp = threadIdx.x >> 5, lane = threadIdx.x & 31;
  const int h = blockIdx.x / 3;
  const int bid = h * 3 + rank;
  if (threadIdx.x == 0) {
    if (sb & 1023) __trap();
    mbar_init(sb + C_BAR, 1); mbar_init(sb + C_BAR + 8, 1); mbar_init(sb + C_BAR + 16, 1);
    asm volatile("fence.mbarrier_init.release.cluster;" ::: "memory");
    mbar_expect(sb + C_BAR, rank < 2 ? 2560 + 2048 : 2560);
    sts32(sb + C_BAR + 32, 0);
  }
  for (int i = threadIdx.x; i < 512; i += 256) sts32(sb + C_SENT + i * 4, SENT);
  fence_async();
  __syncthreads();
  asm volatile("griddepcontrol.launch_dependents;");
  if (lane == 0 && warp < 6 && (warp != 5 || bid < 32)) {
    unsigned char* blk = g_mb + (size_t)(warp < 4 ? 128 + warp : bid + 96 * (warp - 4)) * MB_BLK + bid * 32;
    int best[2] = {1 << 30, 1 << 30};
#pragma unroll 1
    for (int i = 0; i < NPROBE; i++) {
      const uint32_t t0 = clock();
      const uint32_t v = atomicExch((unsigned*)(blk + (i & 1) * 4096), SENT);
      uint32_t t1 = t0;
      asm volatile("{.reg .pred p; setp.ne.u32 p, %1, 0x12345; @p mov.u32 %0, %clock;}" : "+r"(t1) : "r"(v));
      const int d = (int)(t1 - t0);
      if (i >= 2) best[i & 1] = min(best[i & 1], d);
    }
    if (best[1] < best[0]) asm volatile("red.shared.or.b32 [%0], %1;" ::"r"(sb + C_BAR + 32), "r"(1u << warp) : "memory");
  }
  __syncthreads();
  if (warp == 0) {
    uint32_t nb;
    asm volatile("ld.shared.u32 %0, [%1];" : "=r"(nb) : "r"(sb + C_BAR + 32));
    if (lane < 16 && (lane < 8 || bid < 32))
      bulk_s2g(g_mb + (size_t)(bid + (lane >> 3) * 96) * MB_BLK + ((lane >> 1) & 3) * MB_SLOT + ((nb >> (4 + (lane >> 3))) & 1) * 4096 + (lane & 1) * 2048, sb + C_SENT, 2048);
    else if (lane >= 16 && lane < 18 && bid >= 32 && bid < 64)
      bulk_s2g(g_mb + (size_t)(128 + ((bid >> 3) & 3)) * MB_BLK + ((bid >> 1) & 3) * MB_SLOT + (bid & 1) * 4096 + (lane & 1) * 2048, sb + C_SENT, 2048);
    asm volatile("cp.async.bulk.commit_group;" ::: "memory");
    asm volatile("cp.async.bulk.wait_group 0;" ::: "memory");
    __syncwarp();
    if (lane < 2 && (lane == 0 || bid < 32)) {
      asm volatile("fence.acq_rel.gpu;" ::: "memory");
      st_relaxed1(&g_ctrl.place[bid + lane * 96], 1 + ((nb >> (4 + lane)) & 1));
    }
  }
  cluster_sync();
  if (rank < 2) chain_body<true>(P, sb, rank, h);
  else chain_body<false>(P, sb, rank, h);
  cluster_sync();
}

typedef CUresult (*EncodeFn)(CUtensorMap*, CUtensorMapDataType, cuuint32_t, void*, const cuuint64_t*, const cuuint64_t*,
                             const cuuint32_t*, const cuuint32_t*, CUtensorMapInterleave, CUtensorMapSwizzle,
                             CUtensorMapL2promotion, CUtensorMapFloatOOBfill);

static void make_map(EncodeFn enc, CUtensorMap* m, const void* ptr, uint64_t cols, uint64_t rows, uint32_t bcols, uint32_t brows) {
  cuuint64_t dims[2] = {cols, rows};
  cuuint64_t strides[1] = {cols * 2};
  cuuint32_t box[2] = {bcols, brows};
  cuuint32_t es[2] = {1, 1};
  enc(m, CU_TENSOR_MAP_DATA_TYPE_BFLOAT16, 2, (void*)ptr, dims, strides, box, es, CU_TENSOR_MAP_INTERLEAVE_NONE,
      CU_TENSOR_MAP_SWIZZLE_128B, CU_TENSOR_MAP_L2_PROMOTION_L2_256B, CU_TENSOR_MAP_FLOAT_OOB_FILL_NONE);
}

static void make_map4(EncodeFn enc, CUtensorMap* m, const void* ptr, uint64_t rows, uint64_t mats, uint32_t brows, uint32_t bmats) {
  cuuint64_t dims[4] = {64, rows, HD / 64, mats};
  cuuint64_t strides[3] = {HD * 2, 128, rows * HD * 2};
  cuuint32_t box[4] = {64, brows, 2, bmats};
  cuuint32_t es[4] = {1, 1, 1, 1};
  enc(m, CU_TENSOR_MAP_DATA_TYPE_BFLOAT16, 4, (void*)ptr, dims, strides, box, es, CU_TENSOR_MAP_INTERLEAVE_NONE,
      CU_TENSOR_MAP_SWIZZLE_128B, CU_TENSOR_MAP_L2_PROMOTION_L2_256B, CU_TENSOR_MAP_FLOAT_OOB_FILL_NONE);
}

extern "C" void kernel_launch(void* const* d_in, const int* in_sizes, int n_in, void* d_out, int out_size) {
  static EncodeFn enc = nullptr;
  static void *p_qkv, *p_o, *p_kvm;
  static int nsm = 132;
  if (!enc) {
    cudaDriverEntryPointQueryResult qr;
    cudaGetDriverEntryPoint("cuTensorMapEncodeTiled", (void**)&enc, cudaEnableDefault, &qr);
    cudaGetSymbolAddress(&p_qkv, g_qkv);
    cudaGetSymbolAddress(&p_o, g_o);
    cudaGetSymbolAddress(&p_kvm, g_kvm);
    cudaDeviceGetAttribute(&nsm, cudaDevAttrMultiProcessorCount, 0);
    cudaFuncSetAttribute(gemm_kernel, cudaFuncAttributeMaxDynamicSharedMemorySize, G_SMEM);
    cudaFuncSetAttribute(worker_kernel, cudaFuncAttributeMaxDynamicSharedMemorySize, W_SMEM);
    cudaFuncSetAttribute(chain_kernel, cudaFuncAttributeMaxDynamicSharedMemorySize, C_SMEM);
  }
  cudaStream_t st = cudaStreamPerThread;
  GemmMaps m1;
  WorkerMaps wm;
  ChainParams cp;
  for (int p = 0; p < 2; p++) {
    void* const* in = d_in + 7 * p;
    make_map(enc, &m1.a[p], in[0], DM, S_, 64, 128);
    for (int w = 0; w < 3; w++) make_map(enc, &m1.b[p * 3 + w], in[2 + w], HD, DM, 64, 64);
    make_map(enc, &wm.wo[p], in[5], DM, HD, 64, 64);
    cp.mem0[p] = (const bf16*)in[1];
    cp.wq[p] = (const bf16*)in[2]; cp.wk[p] = (const bf16*)in[3]; cp.wv[p] = (const bf16*)in[4]; cp.wo[p] = (const bf16*)in[5];
  }
  make_map(enc, &m1.c, p_qkv, HD, 6 * S_, 64, 64);
  make_map(enc, &cp.kv, p_qkv, HD, 6 * S_, 64, 32);
  make_map4(enc, &wm.qkv4, p_qkv, S_, 6, 32, 3);
  make_map4(enc, &wm.kvm4, p_kvm, MT, 2 * NSEG * 2, 8, 2);
  make_map(enc, &cp.kvm, p_kvm, HD, 2 * NSEG * 16, 64, 8);
  make_map(enc, &wm.o16, p_o, HD, 2 * S_, 64, 16);
  make_map(enc, &wm.o128, p_o, HD, 2 * S_, 64, 128);
  make_map(enc, &wm.o64, p_o, HD, 2 * S_, 64, 64);
  make_map(enc, &wm.out, d_out, 2 * DM, S_, 64, 64);
  wm.xb = m1.a[1];
  for (int w = 0; w < 3; w++) wm.wb[w] = m1.b[3 + w];
  wm.qkv64 = m1.c;

  gemm_kernel<<<nsm, 384, G_SMEM, st>>>(m1);
  {
    cudaLaunchConfig_t cfg = {};
    cfg.gridDim = dim3(96);
    cfg.blockDim = dim3(256); cfg.dynamicSmemBytes = C_SMEM; cfg.stream = st;
    cudaLaunchAttribute at[2];
    at[0].id = cudaLaunchAttributeClusterDimension;
    at[0].val.clusterDim.x = 3; at[0].val.clusterDim.y = 1; at[0].val.clusterDim.z = 1;
    at[1].id = cudaLaunchAttributeProgrammaticStreamSerialization;
    at[1].val.programmaticStreamSerializationAllowed = 1;
    cfg.attrs = at; cfg.numAttrs = 2;
    cudaLaunchKernelEx(&cfg, chain_kernel, cp);
  }
  {
    cudaLaunchConfig_t cfg = {};
    cfg.gridDim = dim3(nsm); cfg.blockDim = dim3(384); cfg.dynamicSmemBytes = W_SMEM; cfg.stream = st;
    cudaLaunchAttribute at[1];
    at[0].id = cudaLaunchAttributeProgrammaticStreamSerialization;
    at[0].val.programmaticStreamSerializationAllowed = 1;
    cfg.attrs = at; cfg.numAttrs = 1;
    cudaLaunchKernelEx(&cfg, worker_kernel, wm);
  }
}
```
